```python
import torch

def _softmax(x, axis=-1):
    return torch.softmax(x, dim=axis)

def _gelu(x):
    return torch.nn.functional.gelu(x, approximate='tanh')

def _silu(x):
    return torch.nn.functional.silu(x)

def _sigmoid(x):
    return torch.sigmoid(x)

def _layernorm(x, axis=-1, eps=1e-05):
    m = x.mean(dim=axis, keepdim=True)
    v = x.var(dim=axis, keepdim=True, unbiased=False)
    return (x - m) / torch.sqrt(v + eps)

def _scatter_add(tgt, idx, src, axis=0):
    return tgt.clone().index_add_(axis, idx, src)

def _segment_sum(src, seg, n):
    out = torch.zeros((n,) + src.shape[1:], dtype=src.dtype)
    return out.index_add_(0, seg, src)

def _pad(x, pw):
    flat = tuple((v for pair in reversed(pw) for v in pair))
    return torch.nn.functional.pad(x, flat)
kernel_name = 'adaLN_cond__mha_block__glu_gated_bilinear__prompt'

def setup_inputs():

    _w = lambda a: (lambda t: t.to(torch.bfloat16) if t.is_floating_point() else t)(torch.as_tensor(a))

    def _A_setup():
        B, S, D, H = (1, 2048, 640, 32)
        return {'x': _w((lambda *s: torch.randn(*s, dtype=torch.bfloat16) * 0.05)(B, S, D)), 'wqkv': _w((lambda *s: torch.randn(*s, dtype=torch.bfloat16) * 0.05)(D, 3 * D)), 'wo': _w((lambda *s: torch.randn(*s, dtype=torch.bfloat16) * 0.05)(D, D))}
    _A_in = _A_setup()

    def _B_setup():
        B, S, D, F = (1, 2048, 640, 1536)
        return {'x': _w((lambda *s: torch.randn(*s, dtype=torch.bfloat16) * 0.05)(B, S, D)), 'w_gate': _w((lambda *s: torch.randn(*s, dtype=torch.bfloat16) * 0.8)(D, F) * D ** (-0.5)), 'w_up': _w((lambda *s: torch.randn(*s, dtype=torch.bfloat16) * 0.8)(D, F) * D ** (-0.5)), 'w_down': _w((lambda *s: torch.randn(*s, dtype=torch.bfloat16) * 0.8)(F, D) * F ** (-0.5))}
    _B_in = _B_setup()
    return {'A_x': _A_in['x'], 'A_wqkv': _A_in['wqkv'], 'A_wo': _A_in['wo'], 'B_x': _B_in['x'], 'B_w_gate': _B_in['w_gate'], 'B_w_up': _B_in['w_up'], 'B_w_down': _B_in['w_down'], 'c': _w((lambda *s: torch.randn(*s, dtype=torch.bfloat16) * 0.1)(1, 640) * 8.0), 'w_mod': _w((lambda *s: torch.randn(*s, dtype=torch.bfloat16) * 0.1)(640, 6 * 640) * 640 ** (-0.5) * 8.0)}

def reference(A_x, A_wqkv, A_wo, B_x, B_w_gate, B_w_up, B_w_down, c, w_mod):

    def _A_ref(x, wqkv, wo):
        B, S, D = x.shape
        H = 32
        Dh = D // H
        qkv = (lambda x, *d: x.permute(*d))((x @ wqkv).reshape(B, S, 3, H, Dh), 2, 0, 3, 1, 4)
        q, k, v = (qkv[0], qkv[1], qkv[2])
        scores = torch.einsum('bhqd,bhkd->bhqk', q, k) * Dh ** (-0.5)
        p = _softmax(scores, axis=-1)
        o = torch.einsum('bhqk,bhkd->bhqd', p, v)
        return (lambda x, *d: x.permute(*d))(o, 0, 2, 1, 3).reshape(B, S, D) @ wo

    def _B_ref(x, w_gate, w_up, w_down):
        g = torch.einsum('bsd,df->bsf', x, w_gate)
        u = torch.einsum('bsd,df->bsf', x, w_up)
        h = g * u
        return torch.einsum('bsf,fd->bsd', h, w_down)
    x = A_x
    mod = (_silu(c) @ w_mod).reshape(c.shape[0], 6, 1, -1)
    sa, ca, ga, sb, cb, gb = (mod[:, 0].clone(), mod[:, 1].clone(), mod[:, 2].clone(), mod[:, 3].clone(), mod[:, 4].clone(), mod[:, 5].clone())
    h = _layernorm(x, axis=-1) * (1 + ca) + sa
    x = x + ga * _A_ref(h, A_wqkv, A_wo)
    h = _layernorm(x, axis=-1) * (1 + cb) + sb
    x = x + gb * _B_ref(h, B_w_gate, B_w_up, B_w_down)
    return x
```

```cpp
#include <cuda_runtime.h>
#include <cuda_bf16.h>
#include <cuda.h>
#include <stdint.h>
#include <math.h>

typedef __nv_bfloat16 bf16;
#define KPAD_LO 0xBF4B4340u
#define KPAD_HI 0x00003AE8u


__device__ __forceinline__ void wgmma_rs_n128_tb1(float (&d)[64], uint32_t a0, uint32_t a1, uint32_t a2, uint32_t a3, uint64_t descB, int scaleD) {
  asm volatile("{\n.reg .pred p;\nsetp.ne.b32 p, %69, 0;\n"
    "wgmma.mma_async.sync.aligned.m64n128k16.f32.bf16.bf16 {%0, %1, %2, %3, %4, %5, %6, %7, %8, %9, %10, %11, %12, %13, %14, %15, %16, %17, %18, %19, %20, %21, %22, %23, %24, %25, %26, %27, %28, %29, %30, %31, %32, %33, %34, %35, %36, %37, %38, %39, %40, %41, %42, %43, %44, %45, %46, %47, %48, %49, %50, %51, %52, %53, %54, %55, %56, %57, %58, %59, %60, %61, %62, %63}, {%64, %65, %66, %67}, %68, p, 1, 1, 1;\n}\n"
    : "+f"(d[0]), "+f"(d[1]), "+f"(d[2]), "+f"(d[3]), "+f"(d[4]), "+f"(d[5]), "+f"(d[6]), "+f"(d[7]), "+f"(d[8]), "+f"(d[9]), "+f"(d[10]), "+f"(d[11]), "+f"(d[12]), "+f"(d[13]), "+f"(d[14]), "+f"(d[15]), "+f"(d[16]), "+f"(d[17]), "+f"(d[18]), "+f"(d[19]), "+f"(d[20]), "+f"(d[21]), "+f"(d[22]), "+f"(d[23]), "+f"(d[24]), "+f"(d[25]), "+f"(d[26]), "+f"(d[27]), "+f"(d[28]), "+f"(d[29]), "+f"(d[30]), "+f"(d[31]), "+f"(d[32]), "+f"(d[33]), "+f"(d[34]), "+f"(d[35]), "+f"(d[36]), "+f"(d[37]), "+f"(d[38]), "+f"(d[39]), "+f"(d[40]), "+f"(d[41]), "+f"(d[42]), "+f"(d[43]), "+f"(d[44]), "+f"(d[45]), "+f"(d[46]), "+f"(d[47]), "+f"(d[48]), "+f"(d[49]), "+f"(d[50]), "+f"(d[51]), "+f"(d[52]), "+f"(d[53]), "+f"(d[54]), "+f"(d[55]), "+f"(d[56]), "+f"(d[57]), "+f"(d[58]), "+f"(d[59]), "+f"(d[60]), "+f"(d[61]), "+f"(d[62]), "+f"(d[63])
    : "r"(a0), "r"(a1), "r"(a2), "r"(a3), "l"(descB), "r"(scaleD));
}
__device__ __forceinline__ void wgmma_rs_n112_tb1(float (&d)[56], uint32_t a0, uint32_t a1, uint32_t a2, uint32_t a3, uint64_t descB, int scaleD) {
  asm volatile("{\n.reg .pred p;\nsetp.ne.b32 p, %61, 0;\n"
    "wgmma.mma_async.sync.aligned.m64n112k16.f32.bf16.bf16 {%0, %1, %2, %3, %4, %5, %6, %7, %8, %9, %10, %11, %12, %13, %14, %15, %16, %17, %18, %19, %20, %21, %22, %23, %24, %25, %26, %27, %28, %29, %30, %31, %32, %33, %34, %35, %36, %37, %38, %39, %40, %41, %42, %43, %44, %45, %46, %47, %48, %49, %50, %51, %52, %53, %54, %55}, {%56, %57, %58, %59}, %60, p, 1, 1, 1;\n}\n"
    : "+f"(d[0]), "+f"(d[1]), "+f"(d[2]), "+f"(d[3]), "+f"(d[4]), "+f"(d[5]), "+f"(d[6]), "+f"(d[7]), "+f"(d[8]), "+f"(d[9]), "+f"(d[10]), "+f"(d[11]), "+f"(d[12]), "+f"(d[13]), "+f"(d[14]), "+f"(d[15]), "+f"(d[16]), "+f"(d[17]), "+f"(d[18]), "+f"(d[19]), "+f"(d[20]), "+f"(d[21]), "+f"(d[22]), "+f"(d[23]), "+f"(d[24]), "+f"(d[25]), "+f"(d[26]), "+f"(d[27]), "+f"(d[28]), "+f"(d[29]), "+f"(d[30]), "+f"(d[31]), "+f"(d[32]), "+f"(d[33]), "+f"(d[34]), "+f"(d[35]), "+f"(d[36]), "+f"(d[37]), "+f"(d[38]), "+f"(d[39]), "+f"(d[40]), "+f"(d[41]), "+f"(d[42]), "+f"(d[43]), "+f"(d[44]), "+f"(d[45]), "+f"(d[46]), "+f"(d[47]), "+f"(d[48]), "+f"(d[49]), "+f"(d[50]), "+f"(d[51]), "+f"(d[52]), "+f"(d[53]), "+f"(d[54]), "+f"(d[55])
    : "r"(a0), "r"(a1), "r"(a2), "r"(a3), "l"(descB), "r"(scaleD));
}
__device__ __forceinline__ void wgmma_rs_n192_tb1(float (&d)[96], uint32_t a0, uint32_t a1, uint32_t a2, uint32_t a3, uint64_t descB, int scaleD) {
  asm volatile("{\n.reg .pred p;\nsetp.ne.b32 p, %101, 0;\n"
    "wgmma.mma_async.sync.aligned.m64n192k16.f32.bf16.bf16 {%0, %1, %2, %3, %4, %5, %6, %7, %8, %9, %10, %11, %12, %13, %14, %15, %16, %17, %18, %19, %20, %21, %22, %23, %24, %25, %26, %27, %28, %29, %30, %31, %32, %33, %34, %35, %36, %37, %38, %39, %40, %41, %42, %43, %44, %45, %46, %47, %48, %49, %50, %51, %52, %53, %54, %55, %56, %57, %58, %59, %60, %61, %62, %63, %64, %65, %66, %67, %68, %69, %70, %71, %72, %73, %74, %75, %76, %77, %78, %79, %80, %81, %82, %83, %84, %85, %86, %87, %88, %89, %90, %91, %92, %93, %94, %95}, {%96, %97, %98, %99}, %100, p, 1, 1, 1;\n}\n"
    : "+f"(d[0]), "+f"(d[1]), "+f"(d[2]), "+f"(d[3]), "+f"(d[4]), "+f"(d[5]), "+f"(d[6]), "+f"(d[7]), "+f"(d[8]), "+f"(d[9]), "+f"(d[10]), "+f"(d[11]), "+f"(d[12]), "+f"(d[13]), "+f"(d[14]), "+f"(d[15]), "+f"(d[16]), "+f"(d[17]), "+f"(d[18]), "+f"(d[19]), "+f"(d[20]), "+f"(d[21]), "+f"(d[22]), "+f"(d[23]), "+f"(d[24]), "+f"(d[25]), "+f"(d[26]), "+f"(d[27]), "+f"(d[28]), "+f"(d[29]), "+f"(d[30]), "+f"(d[31]), "+f"(d[32]), "+f"(d[33]), "+f"(d[34]), "+f"(d[35]), "+f"(d[36]), "+f"(d[37]), "+f"(d[38]), "+f"(d[39]), "+f"(d[40]), "+f"(d[41]), "+f"(d[42]), "+f"(d[43]), "+f"(d[44]), "+f"(d[45]), "+f"(d[46]), "+f"(d[47]), "+f"(d[48]), "+f"(d[49]), "+f"(d[50]), "+f"(d[51]), "+f"(d[52]), "+f"(d[53]), "+f"(d[54]), "+f"(d[55]), "+f"(d[56]), "+f"(d[57]), "+f"(d[58]), "+f"(d[59]), "+f"(d[60]), "+f"(d[61]), "+f"(d[62]), "+f"(d[63]), "+f"(d[64]), "+f"(d[65]), "+f"(d[66]), "+f"(d[67]), "+f"(d[68]), "+f"(d[69]), "+f"(d[70]), "+f"(d[71]), "+f"(d[72]), "+f"(d[73]), "+f"(d[74]), "+f"(d[75]), "+f"(d[76]), "+f"(d[77]), "+f"(d[78]), "+f"(d[79]), "+f"(d[80]), "+f"(d[81]), "+f"(d[82]), "+f"(d[83]), "+f"(d[84]), "+f"(d[85]), "+f"(d[86]), "+f"(d[87]), "+f"(d[88]), "+f"(d[89]), "+f"(d[90]), "+f"(d[91]), "+f"(d[92]), "+f"(d[93]), "+f"(d[94]), "+f"(d[95])
    : "r"(a0), "r"(a1), "r"(a2), "r"(a3), "l"(descB), "r"(scaleD));
}
__device__ __forceinline__ void wgmma_ss_n128_tb1(float (&d)[64], uint64_t descA, uint64_t descB, int scaleD) {
  asm volatile("{\n.reg .pred p;\nsetp.ne.b32 p, %66, 0;\n"
    "wgmma.mma_async.sync.aligned.m64n128k16.f32.bf16.bf16 {%0, %1, %2, %3, %4, %5, %6, %7, %8, %9, %10, %11, %12, %13, %14, %15, %16, %17, %18, %19, %20, %21, %22, %23, %24, %25, %26, %27, %28, %29, %30, %31, %32, %33, %34, %35, %36, %37, %38, %39, %40, %41, %42, %43, %44, %45, %46, %47, %48, %49, %50, %51, %52, %53, %54, %55, %56, %57, %58, %59, %60, %61, %62, %63}, %64, %65, p, 1, 1, 0, 1;\n}\n"
    : "+f"(d[0]), "+f"(d[1]), "+f"(d[2]), "+f"(d[3]), "+f"(d[4]), "+f"(d[5]), "+f"(d[6]), "+f"(d[7]), "+f"(d[8]), "+f"(d[9]), "+f"(d[10]), "+f"(d[11]), "+f"(d[12]), "+f"(d[13]), "+f"(d[14]), "+f"(d[15]), "+f"(d[16]), "+f"(d[17]), "+f"(d[18]), "+f"(d[19]), "+f"(d[20]), "+f"(d[21]), "+f"(d[22]), "+f"(d[23]), "+f"(d[24]), "+f"(d[25]), "+f"(d[26]), "+f"(d[27]), "+f"(d[28]), "+f"(d[29]), "+f"(d[30]), "+f"(d[31]), "+f"(d[32]), "+f"(d[33]), "+f"(d[34]), "+f"(d[35]), "+f"(d[36]), "+f"(d[37]), "+f"(d[38]), "+f"(d[39]), "+f"(d[40]), "+f"(d[41]), "+f"(d[42]), "+f"(d[43]), "+f"(d[44]), "+f"(d[45]), "+f"(d[46]), "+f"(d[47]), "+f"(d[48]), "+f"(d[49]), "+f"(d[50]), "+f"(d[51]), "+f"(d[52]), "+f"(d[53]), "+f"(d[54]), "+f"(d[55]), "+f"(d[56]), "+f"(d[57]), "+f"(d[58]), "+f"(d[59]), "+f"(d[60]), "+f"(d[61]), "+f"(d[62]), "+f"(d[63])
    : "l"(descA), "l"(descB), "r"(scaleD));
}
__device__ __forceinline__ void wgmma_rs_n64_tb0(float (&d)[32], uint32_t a0, uint32_t a1, uint32_t a2, uint32_t a3, uint64_t descB, int scaleD) {
  asm volatile("{\n.reg .pred p;\nsetp.ne.b32 p, %37, 0;\n"
    "wgmma.mma_async.sync.aligned.m64n64k16.f32.bf16.bf16 {%0, %1, %2, %3, %4, %5, %6, %7, %8, %9, %10, %11, %12, %13, %14, %15, %16, %17, %18, %19, %20, %21, %22, %23, %24, %25, %26, %27, %28, %29, %30, %31}, {%32, %33, %34, %35}, %36, p, 1, 1, 0;\n}\n"
    : "+f"(d[0]), "+f"(d[1]), "+f"(d[2]), "+f"(d[3]), "+f"(d[4]), "+f"(d[5]), "+f"(d[6]), "+f"(d[7]), "+f"(d[8]), "+f"(d[9]), "+f"(d[10]), "+f"(d[11]), "+f"(d[12]), "+f"(d[13]), "+f"(d[14]), "+f"(d[15]), "+f"(d[16]), "+f"(d[17]), "+f"(d[18]), "+f"(d[19]), "+f"(d[20]), "+f"(d[21]), "+f"(d[22]), "+f"(d[23]), "+f"(d[24]), "+f"(d[25]), "+f"(d[26]), "+f"(d[27]), "+f"(d[28]), "+f"(d[29]), "+f"(d[30]), "+f"(d[31])
    : "r"(a0), "r"(a1), "r"(a2), "r"(a3), "l"(descB), "r"(scaleD));
}
__device__ __forceinline__ void wgmma_rs_n24_tb1(float (&d)[12], uint32_t a0, uint32_t a1, uint32_t a2, uint32_t a3, uint64_t descB, int scaleD) {
  asm volatile("{\n.reg .pred p;\nsetp.ne.b32 p, %17, 0;\n"
    "wgmma.mma_async.sync.aligned.m64n24k16.f32.bf16.bf16 {%0, %1, %2, %3, %4, %5, %6, %7, %8, %9, %10, %11}, {%12, %13, %14, %15}, %16, p, 1, 1, 1;\n}\n"
    : "+f"(d[0]), "+f"(d[1]), "+f"(d[2]), "+f"(d[3]), "+f"(d[4]), "+f"(d[5]), "+f"(d[6]), "+f"(d[7]), "+f"(d[8]), "+f"(d[9]), "+f"(d[10]), "+f"(d[11])
    : "r"(a0), "r"(a1), "r"(a2), "r"(a3), "l"(descB), "r"(scaleD));
}
__device__ __forceinline__ void wgmma_rs_n64_tb1(float (&d)[32], uint32_t a0, uint32_t a1, uint32_t a2, uint32_t a3, uint64_t descB, int scaleD) {
  asm volatile("{\n.reg .pred p;\nsetp.ne.b32 p, %37, 0;\n"
    "wgmma.mma_async.sync.aligned.m64n64k16.f32.bf16.bf16 {%0, %1, %2, %3, %4, %5, %6, %7, %8, %9, %10, %11, %12, %13, %14, %15, %16, %17, %18, %19, %20, %21, %22, %23, %24, %25, %26, %27, %28, %29, %30, %31}, {%32, %33, %34, %35}, %36, p, 1, 1, 1;\n}\n"
    : "+f"(d[0]), "+f"(d[1]), "+f"(d[2]), "+f"(d[3]), "+f"(d[4]), "+f"(d[5]), "+f"(d[6]), "+f"(d[7]), "+f"(d[8]), "+f"(d[9]), "+f"(d[10]), "+f"(d[11]), "+f"(d[12]), "+f"(d[13]), "+f"(d[14]), "+f"(d[15]), "+f"(d[16]), "+f"(d[17]), "+f"(d[18]), "+f"(d[19]), "+f"(d[20]), "+f"(d[21]), "+f"(d[22]), "+f"(d[23]), "+f"(d[24]), "+f"(d[25]), "+f"(d[26]), "+f"(d[27]), "+f"(d[28]), "+f"(d[29]), "+f"(d[30]), "+f"(d[31])
    : "r"(a0), "r"(a1), "r"(a2), "r"(a3), "l"(descB), "r"(scaleD));
}
__device__ __forceinline__ void wgmma_rs_n16_tb1(float (&d)[8], uint32_t a0, uint32_t a1, uint32_t a2, uint32_t a3, uint64_t descB, int scaleD) {
  asm volatile("{\n.reg .pred p;\nsetp.ne.b32 p, %13, 0;\n"
    "wgmma.mma_async.sync.aligned.m64n16k16.f32.bf16.bf16 {%0, %1, %2, %3, %4, %5, %6, %7}, {%8, %9, %10, %11}, %12, p, 1, 1, 1;\n}\n"
    : "+f"(d[0]), "+f"(d[1]), "+f"(d[2]), "+f"(d[3]), "+f"(d[4]), "+f"(d[5]), "+f"(d[6]), "+f"(d[7])
    : "r"(a0), "r"(a1), "r"(a2), "r"(a3), "l"(descB), "r"(scaleD));
}


constexpr int S_ = 2048, D_ = 640, F_ = 1536;
constexpr float LN_EPS = 1e-5f;
constexpr uint32_t PMASK = 0xB5u;
constexpr float QSCALE = 0.22360679774997896f * 1.4426950408889634f;

__device__ __align__(16) uint32_t g_mod1[5 * 2 * D_];
__device__ uint4 g_ln2[D_ / 4];
__device__ float g_ga[D_], g_gb[D_];
__device__ uint2 g_stats1[S_];
__device__ unsigned int g_flags[32 * 32];
__device__ __align__(128) float2 g_stats2[8 * S_];
__device__ __align__(1024) bf16 g_q[32 * 32 * 1536];
__device__ __align__(1024) bf16 g_kv[32 * 32 * 3072];
__device__ unsigned int g_fq[16 * 32];
__device__ __align__(1024) bf16 g_o[S_ * D_];
__device__ __align__(1024) bf16 g_x2[S_ * D_];
__device__ __align__(1024) bf16 g_hh[S_ * F_];

#define WG_FENCE() asm volatile("wgmma.fence.sync.aligned;\n" ::: "memory")
#define WG_COMMIT() asm volatile("wgmma.commit_group.sync.aligned;\n" ::: "memory")
#define WG_WAIT(n) asm volatile("wgmma.wait_group.sync.aligned %0;\n" :: "n"(n) : "memory")
#define PDL_TRIGGER() asm volatile("griddepcontrol.launch_dependents;\n" ::: "memory")
#define PDL_WAIT() asm volatile("griddepcontrol.wait;\n" ::: "memory")

template <int N> __device__ __forceinline__ void fence_regs(float (&r)[N]) {
#pragma unroll
  for (int i = 0; i < N; i++) asm volatile("" : "+f"(r[i]) :: "memory");
}
template <int N> __device__ __forceinline__ void fence_regs(uint32_t (&r)[N]) {
#pragma unroll
  for (int i = 0; i < N; i++) asm volatile("" : "+r"(r[i]) :: "memory");
}
__device__ __forceinline__ uint32_t smem_u32(const void* p) { return (uint32_t)__cvta_generic_to_shared(p); }
__device__ __forceinline__ uint64_t mkd(uint32_t lo, uint32_t hi) {
  uint64_t d; asm("mov.b64 %0, {%1, %2};\n" : "=l"(d) : "r"(lo), "r"(hi)); return d;
}
__device__ __forceinline__ void mbar_init(uint32_t bar, int cnt) {
  asm volatile("mbarrier.init.shared::cta.b64 [%0], %1;\n" :: "r"(bar), "r"(cnt));
}
__device__ __forceinline__ void mbar_expect_tx(uint32_t bar, int bytes) {
  asm volatile("mbarrier.arrive.expect_tx.shared::cta.b64 _, [%0], %1;\n" :: "r"(bar), "r"(bytes) : "memory");
}
__device__ __forceinline__ void mbar_wait(uint32_t bar, int parity) {
  asm volatile("{\n.reg .pred p;\n.reg .b32 c;\nmov.b32 c, 0;\n"
               "MW_%=:\nmbarrier.try_wait.parity.shared::cta.b64 p, [%0], %1;\n@p bra MD_%=;\n"
               "add.u32 c, c, 1;\nsetp.lt.u32 p, c, 0x400000;\n@p bra MW_%=;\ntrap;\nMD_%=:\n}\n" :: "r"(bar), "r"(parity) : "memory");
}
__device__ __forceinline__ void mbar_arrive(uint32_t bar) { asm volatile("mbarrier.arrive.shared::cta.b64 _, [%0];\n" :: "r"(bar) : "memory"); }
__device__ __forceinline__ void mbar_arrive_cluster(uint32_t bar, uint32_t cta) {
  asm volatile("{\n.reg .b32 r;\nmapa.shared::cluster.u32 r, %0, %1;\nmbarrier.arrive.shared::cluster.b64 _, [r];\n}\n"
               :: "r"(bar), "r"(cta) : "memory");
}
__device__ __forceinline__ void cluster_sync() {
  asm volatile("barrier.cluster.arrive.relaxed.aligned;\nbarrier.cluster.wait.acquire.aligned;\n" ::: "memory");
}
__device__ __forceinline__ int fresh_tid() { int r; asm volatile("mov.u32 %0, %%tid.x;\n" : "=r"(r)); return r; }
__device__ __forceinline__ uint32_t cluster_rank() { uint32_t r; asm("mov.u32 %0, %%cluster_ctarank;\n" : "=r"(r)); return r; }
__device__ __forceinline__ void bulk_g2s(uint32_t dst, const void* src, int bytes, uint32_t bar) {
  asm volatile("cp.async.bulk.shared::cluster.global.mbarrier::complete_tx::bytes [%0], [%1], %2, [%3];\n"
               :: "r"(dst), "l"(src), "r"(bytes), "r"(bar) : "memory");
}
__device__ __forceinline__ void tma_load(uint32_t dst, const CUtensorMap* tm, int c0, int c1, uint32_t bar) {
  asm volatile("cp.async.bulk.tensor.2d.shared::cluster.global.mbarrier::complete_tx::bytes [%0], [%1, {%3, %4}], [%2];\n"
               :: "r"(dst), "l"(tm), "r"(bar), "r"(c0), "r"(c1) : "memory");
}
__device__ __forceinline__ void tma_load_mc(uint32_t dst, const CUtensorMap* tm, int c0, int c1, uint32_t bar) {
  asm volatile("cp.async.bulk.tensor.2d.shared::cluster.global.mbarrier::complete_tx::bytes.multicast::cluster [%0], [%1, {%3, %4}], [%2], %5;\n"
               :: "r"(dst), "l"(tm), "r"(bar), "r"(c0), "r"(c1), "h"((uint16_t)3) : "memory");
}
__device__ __forceinline__ void tma_store(const CUtensorMap* tm, int c0, int c1, uint32_t src) {
  asm volatile("cp.async.bulk.tensor.2d.global.shared::cta.bulk_group [%0, {%2, %3}], [%1];\n"
               :: "l"(tm), "r"(src), "r"(c0), "r"(c1) : "memory");
}
__device__ __forceinline__ void tma_prefetch_desc(const CUtensorMap* tm) {
  asm volatile("prefetch.tensormap [%0];\n" :: "l"(tm) : "memory");
}
__device__ __forceinline__ void l2_prefetch(const void* p, int bytes) {
  asm volatile("cp.async.bulk.prefetch.L2.global [%0], %1;\n" :: "l"(p), "r"(bytes) : "memory");
}
__device__ __forceinline__ void named_arrive(int id, int n) { asm volatile("bar.arrive %0, %1;\n" :: "r"(id), "r"(n) : "memory"); }
__device__ __forceinline__ void named_bar(int id, int n) { asm volatile("bar.sync %0, %1;\n" :: "r"(id), "r"(n) : "memory"); }
__device__ __forceinline__ float ex2(float x) { float y; asm("ex2.approx.ftz.f32 %0, %1;\n" : "=f"(y) : "f"(x)); return y; }
__device__ __forceinline__ uint32_t pack_bf16(float lo, float hi) {
  uint32_t r; asm("cvt.rn.bf16x2.f32 %0, %1, %2;\n" : "=r"(r) : "f"(hi), "f"(lo)); return r;
}
__device__ __forceinline__ float bf_lo(uint32_t u) { return __uint_as_float(u << 16); }
__device__ __forceinline__ float bf_hi(uint32_t u) { return __uint_as_float(u & 0xFFFF0000u); }
__device__ __forceinline__ float bf_round(float x) { return __bfloat162float(__float2bfloat16(x)); }
__device__ __forceinline__ void ldsm_x4(uint32_t (&r)[4], uint32_t addr) {
  asm volatile("ldmatrix.sync.aligned.m8n8.x4.shared.b16 {%0, %1, %2, %3}, [%4];\n"
               : "=r"(r[0]), "=r"(r[1]), "=r"(r[2]), "=r"(r[3]) : "r"(addr) : "memory");
}
__device__ __forceinline__ uint32_t lds32(uint32_t addr) { uint32_t v; asm volatile("ld.shared.b32 %0, [%1];\n" : "=r"(v) : "r"(addr) : "memory"); return v; }
__device__ __forceinline__ void sts32(uint32_t addr, uint32_t v) { asm volatile("st.shared.b32 [%0], %1;\n" :: "r"(addr), "r"(v) : "memory"); }

constexpr uint32_t DESC_HI_SW128 = (1024 >> 4) | (1u << 30);
__device__ __forceinline__ uint32_t desc_lo(uint32_t addr, uint32_t lbo) { return ((addr & 0x3FFFF) >> 4) | ((lbo >> 4) << 16); }

__device__ __forceinline__ float silu_bf(bf16 c) {
  float x = __bfloat162float(c);
  return bf_round(__fdividef(x, 1.0f + __expf(-x)));
}
__device__ __forceinline__ int ln_slot(int c) { return (c >> 4) * 32 + ((c >> 1) & 3) * 8 + ((c >> 3) & 1) * 4 + (c & 1); }
__device__ __forceinline__ void store_mod(int part, int c, float v) {
  v = bf_round(v);
  bf16* l2 = reinterpret_cast<bf16*>(g_ln2);
  if (part == 2) g_ga[c] = v;
  else if (part == 3) l2[ln_slot(c) + 2] = __float2bfloat16(v);
  else if (part == 4) l2[ln_slot(c)] = __float2bfloat16(1.0f + v);
  else g_gb[c] = v;
}

__device__ __forceinline__ uint32_t hfma2_bf16(uint32_t a, uint32_t b, uint32_t c) {
  uint32_t r; asm("fma.rn.bf16x2 %0, %1, %2, %3;\n" : "=r"(r) : "r"(a), "r"(b), "r"(c)); return r;
}
__device__ __forceinline__ uint32_t hmul2_bf16(uint32_t a, uint32_t b) {
  uint32_t r; asm("mul.rn.bf16x2 %0, %1, %2;\n" : "=r"(r) : "r"(a), "r"(b)); return r;
}
__device__ __forceinline__ void lds128u(uint32_t (&r)[4], uint32_t addr) {
  asm volatile("ld.shared.v4.b32 {%0, %1, %2, %3}, [%4];\n" : "=r"(r[0]), "=r"(r[1]), "=r"(r[2]), "=r"(r[3]) : "r"(addr) : "memory");
}
__device__ __forceinline__ void ln_frag(uint32_t (&a)[4], const uint32_t (&r)[4], const uint32_t (&p)[4], float2 st0, float2 st1) {
  a[0] = hfma2_bf16(pack_bf16(fmaf(bf_lo(r[0]), st0.x, st0.y), fmaf(bf_hi(r[0]), st0.x, st0.y)), p[0], p[1]);
  a[1] = hfma2_bf16(pack_bf16(fmaf(bf_lo(r[1]), st1.x, st1.y), fmaf(bf_hi(r[1]), st1.x, st1.y)), p[0], p[1]);
  a[2] = hfma2_bf16(pack_bf16(fmaf(bf_lo(r[2]), st0.x, st0.y), fmaf(bf_hi(r[2]), st0.x, st0.y)), p[2], p[3]);
  a[3] = hfma2_bf16(pack_bf16(fmaf(bf_lo(r[3]), st1.x, st1.y), fmaf(bf_hi(r[3]), st1.x, st1.y)), p[2], p[3]);
}

constexpr int K2_ST = 4, K2_STAGE = 16384 + 32768;
constexpr int KA_SMEM = K2_ST * K2_STAGE + 4096 + 1024;
#define P1W 1
#define POLL_NS 1500
#define C4W 4
#define K2E 2
#define K2L 2
constexpr int K2_LEAD = K2L, K2_EARLY = K2E;
#define P1U 10
constexpr int P1_UNROLL = P1U;
__device__ __forceinline__ void k2_load(uint32_t sb, uint32_t fb, const CUtensorMap* tm_x, const CUtensorMap* tm_w, int kb, int m0, int n0, int rank, int part) {
  const int s = kb % K2_ST;
  const uint32_t a = sb + s * K2_STAGE;
  if (part == 0) {
    mbar_expect_tx(fb + 8 * s, K2_STAGE);
    tma_load(a, tm_x, kb * 64, m0, fb + 8 * s);
  } else {
    const int gi = rank * 2 + part - 1;
    tma_load_mc(a + 16384 + gi * 8192, tm_w, n0 + gi * 64, kb * 64, fb + 8 * s);
  }
}
__device__ __forceinline__ uint32_t nz_bits(float v) { const uint32_t u = __float_as_uint(v); return u ? u : 0x80000000u; }
__device__ __forceinline__ void flag_wait(const unsigned int* f, unsigned int n) {
  asm volatile("{\n.reg .pred p;\n.reg .b32 v, c;\nmov.b32 c, 0;\n"
               "FW_%=:\nld.relaxed.gpu.global.u32 v, [%0];\nsetp.ge.u32 p, v, %1;\n@p bra FD_%=;\n"
               "add.u32 c, c, 1;\nsetp.lt.u32 p, c, 0x400000;\n@p bra FW_%=;\ntrap;\nFD_%=:\n"
               "fence.proxy.async.global;\n}\n" :: "l"(f), "r"(n) : "memory");
}
__device__ __forceinline__ void qkv_store(uint32_t stg, int hr, int nblk, int step) {
  const int ha = nblk * 12 + hr;
  uint8_t* dst = ha < 32 ? reinterpret_cast<uint8_t*>(g_q) + ((size_t)ha * 32 + step) * 3072
                         : reinterpret_cast<uint8_t*>(g_kv) + ((size_t)(ha & 31) * 32 + step) * 6144 + (ha >= 64 ? 3072 : 0);
  asm volatile("cp.async.bulk.global.shared::cta.bulk_group [%0], [%1], %2;\n" :: "l"(dst), "r"(stg + hr * 3072), "r"(3072) : "memory");
  asm volatile("cp.async.bulk.commit_group;\n" ::: "memory");
}
__device__ __forceinline__ void qkv_publish(unsigned int* f, int lane) {
  asm volatile("cp.async.bulk.wait_group 0;\n" ::: "memory");
  asm volatile("fence.proxy.async.global;\n" ::: "memory");
  __syncwarp();
  if (lane == 0) asm volatile("red.release.gpu.global.add.u32 [%0], 1;\n" :: "l"(f) : "memory");
}
__device__ __forceinline__ void qkv_flags_wait(int head, int half) {
  const unsigned int* f = g_fq + half * 32;
  asm volatile("{\n.reg .pred p;\n.reg .b32 u, v, w, c;\nmov.b32 c, 0;\n"
               "FW_%=:\nld.relaxed.gpu.global.u32 u, [%0];\nld.relaxed.gpu.global.u32 v, [%1];\nld.relaxed.gpu.global.u32 w, [%2];\n"
               "min.u32 u, u, v;\nmin.u32 u, u, w;\nsetp.ge.u32 p, u, 16;\n@p bra FD_%=;\n"
               "add.u32 c, c, 1;\nsetp.lt.u32 p, c, 0x400000;\n@p bra FW_%=;\ntrap;\nFD_%=:\n"
               "fence.proxy.async.global;\n}\n"
               :: "l"(f + (head / 12) * 64), "l"(f + ((32 + head) / 12) * 64), "l"(f + ((64 + head) / 12) * 64) : "memory");
}
__device__ __forceinline__ uint32_t exp2_pair(float x0, float x1) {
  const uint32_t u = __byte_perm(__float_as_uint(x0), __float_as_uint(x1), 0x6521);
  const uint32_t e = u & 0xFF80FF80u;
  uint32_t gh; asm("lop3.b32 %0, %1, %2, 0x3F003F00, 0xBA;\n" : "=r"(gh) : "r"(u), "r"(e));
  return hfma2_bf16(u, gh, e);
}
__device__ __forceinline__ void dadd(uint64_t& d) {
  asm volatile("{\n.reg .b32 lo, hi;\nmov.b64 {lo, hi}, %0;\nadd.u32 lo, lo, 768;\nmov.b64 %0, {lo, hi};\n}\n" : "+l"(d));
}
#define ATTN_STEP(PM, K0, K1, V0, V1, V2, V3)                                                  \
  WG_WAIT(0);                                                                               \
  fence_regs(s); fence_regs(o);                                                             \
  _Pragma("unroll") for (int c = 0; c < 8; c++) {                                           \
    if (((PM) >> c) & 1) {                                                                  \
      p[2 * c] = exp2_pair(s[4 * c], s[4 * c + 1]);                                         \
      p[2 * c + 1] = exp2_pair(s[4 * c + 2], s[4 * c + 3]);                                 \
    } else {                                                                                \
      p[2 * c] = pack_bf16(ex2(s[4 * c]), ex2(s[4 * c + 1]));                               \
      p[2 * c + 1] = pack_bf16(ex2(s[4 * c + 2]), ex2(s[4 * c + 3]));                       \
    }                                                                                       \
  }                                                                                         \
  fence_regs(p);                                                                            \
  WG_FENCE();                                                                               \
  wgmma_rs_n24_tb1(o, p[0], p[1], p[2], p[3], V0, 1);                                       \
  wgmma_rs_n24_tb1(o, p[4], p[5], p[6], p[7], V1, 1);                                       \
  wgmma_rs_n24_tb1(o, p[8], p[9], p[10], p[11], V2, 1);                                     \
  wgmma_rs_n24_tb1(o, p[12], p[13], p[14], p[15], V3, 1);                                   \
  wgmma_rs_n64_tb0(s, a0, a1, a2, a3, K0, 0);         \
  wgmma_rs_n64_tb0(s, a4, a5, z0, z1, K1, 1);                                               \
  WG_COMMIT();                                                                              \
  dadd(K0); dadd(K1); dadd(V0); dadd(V1); dadd(V2); dadd(V3);
__device__ __forceinline__ void kv_load(uint32_t sb, uint32_t bb, int head, int ch) {
  const int start = ch ? (6144 << ch) : 0, bytes = ch ? (6144 << ch) : 12288;
  mbar_expect_tx(bb + 8 * ch, bytes);
  bulk_g2s(sb + start, reinterpret_cast<const uint8_t*>(g_kv) + (size_t)head * 196608 + start, bytes, bb + 8 * ch);
}
__device__ __forceinline__ void q_load(uint32_t (&a)[6], int head, int step, int warp, int lane, float& qn) {
  const int t = lane & 3;
  const uint32_t* q0 = reinterpret_cast<const uint32_t*>(g_q) + ((size_t)head * 32 + step) * 768 + warp * 192 + lane;
  a[0] = __ldcg(q0); a[1] = __ldcg(q0 + 96); a[2] = __ldcg(q0 + 32); a[3] = __ldcg(q0 + 128);
  a[4] = a[5] = 0;
  if (t < 2) { a[4] = __ldcg(q0 + 64); a[5] = __ldcg(q0 + 160); }
  float n0 = 0.f, n1 = 0.f;
#pragma unroll
  for (int i = 0; i < 3; i++) {
    n0 += bf_lo(a[2 * i]) * bf_lo(a[2 * i]) + bf_hi(a[2 * i]) * bf_hi(a[2 * i]);
    n1 += bf_lo(a[2 * i + 1]) * bf_lo(a[2 * i + 1]) + bf_hi(a[2 * i + 1]) * bf_hi(a[2 * i + 1]);
  }
  n0 += __shfl_xor_sync(0xffffffffu, n0, 1); n0 += __shfl_xor_sync(0xffffffffu, n0, 2);
  n1 += __shfl_xor_sync(0xffffffffu, n1, 1); n1 += __shfl_xor_sync(0xffffffffu, n1, 2);
  qn = __uint_as_float(max(max(__float_as_uint(n0), __float_as_uint(n1)), __float_as_uint(qn)));
}
__device__ __forceinline__ void attn_store(float (&o)[12], int row0, int head, int lane) {
  const int t = lane & 3;
  const float l0 = __shfl_sync(0xffffffffu, o[8], (lane & ~3) | 2);
  const float l1 = __shfl_sync(0xffffffffu, o[10], (lane & ~3) | 2);
  const float r0 = __fdividef(1.0f, l0), r1 = __fdividef(1.0f, l1);
  uint32_t* o0 = reinterpret_cast<uint32_t*>(g_o + (size_t)row0 * D_ + head * 20);
  uint32_t* o1 = o0 + 8 * (D_ / 2);
  o0[t] = pack_bf16(o[0] * r0, o[1] * r0); o1[t] = pack_bf16(o[2] * r1, o[3] * r1);
  o0[t + 4] = pack_bf16(o[4] * r0, o[5] * r0); o1[t + 4] = pack_bf16(o[6] * r1, o[7] * r1);
  if (t < 2) { o0[t + 8] = pack_bf16(o[8] * r0, o[9] * r0); o1[t + 8] = pack_bf16(o[10] * r1, o[11] * r1); }
}

struct AttnArgs { const bf16 *wo, *wg, *wu, *wd; };
__device__ __forceinline__ void attn_phase(uint32_t sb, uint32_t bb, uint32_t* s_misc, const AttnArgs& ar) {
  const int tid = fresh_tid(), wid = __shfl_sync(0xffffffffu, tid >> 5, 0), head = blockIdx.x >> 2, quarter = blockIdx.x & 3;
  const int wg = wid >> 2, warp = wid & 3, lane = tid & 31, g = lane >> 2, t = lane & 3;
  const uint32_t klo0 = desc_lo(sb, 128), vlo0 = desc_lo(sb + 3072, 384);
  const uint32_t z0 = *reinterpret_cast<volatile uint32_t*>(&s_misc[1]), z1 = *reinterpret_cast<volatile uint32_t*>(&s_misc[2]);
  const uint32_t qpad = (t == 2) ? 0x3F803F80u : 0x00003F80u;
  float qn = 0.f;
  uint32_t an[6];
  mbar_wait(bb + 48, 0);
  q_load(an, head, quarter * 4 + wg, warp, lane, qn);
  mbar_wait(bb, 0);
#pragma unroll 1
  for (int tile = 0; tile < 2; tile++) {
    const uint32_t a0 = an[0], a1 = an[1], a2 = an[2], a3 = an[3], a4 = t < 2 ? an[4] : qpad, a5 = t < 2 ? an[5] : qpad;
    float o[12], s[32];
    uint32_t p[16];
    uint64_t dk0 = mkd(klo0 + 384, 24), dk1 = mkd(klo0 + 384 + 16 - (8 << 16), 24);
    uint64_t ek0 = mkd(klo0 + 768, 24), ek1 = mkd(klo0 + 768 + 16 - (8 << 16), 24);
    uint64_t dv0 = mkd(vlo0, 8), dv1 = mkd(vlo0 + 48, 8), dv2 = mkd(vlo0 + 96, 8), dv3 = mkd(vlo0 + 144, 8);
    uint64_t ev0 = mkd(vlo0 + 384, 8), ev1 = mkd(vlo0 + 432, 8), ev2 = mkd(vlo0 + 480, 8), ev3 = mkd(vlo0 + 528, 8);
#pragma unroll
    for (int i = 0; i < 12; i++) o[i] = 0.f;
    fence_regs(o);
    WG_FENCE();
    wgmma_rs_n64_tb0(s, a0, a1, a2, a3, mkd(klo0, 24), 0);
    wgmma_rs_n64_tb0(s, a4, a5, z0, z1, mkd(klo0 + 16 - (8 << 16), 24), 1);
    WG_COMMIT();
#pragma unroll 1
    for (int dd = tile ? 8 : 0; dd < 9; dd++) {
      int n = 16;
      if (dd < 8) {
        n = 1;
        if (dd < 2) {
          if (wid == 4 * (dd + 1) && lane == 0) kv_load(sb, bb, head, dd + 2);
          if (dd == 0 && wid == 12 && lane < 12) qkv_store(sb + 3 * K2_STAGE, lane, (blockIdx.x >> 1) & 7, 16 + (blockIdx.x >> 4) * 2 + (blockIdx.x & 1));
          mbar_wait(bb + 8 * (dd + 1), 0);
        } else if (dd == 2) {
          if (wid == 12) {
            qkv_publish(&g_fq[((blockIdx.x >> 1) & 7) * 64 + 32], lane);
            if (lane == 0) mbar_arrive(bb + 56);
          }
        } else if (dd == 3) {
          mbar_wait(bb + 24, 0);
        } else if (dd == 4) {
          if (wid == C4W) {
            mbar_wait(bb + 56, 0);
            qkv_flags_wait(head, 1);
            if (lane == 0) kv_load(sb, bb, head, 4);
          }
          n = 3; dd = 6;
        } else {
          mbar_wait(bb + 32, 0);
          q_load(an, head, 16 + quarter * 4 + wg, warp, lane, qn);
          n = 9; dd = 8;
        }
      }
#pragma unroll 1
      for (; n > 0; n--) {
        ATTN_STEP(PMASK, dk0, dk1, dv0, dv1, dv2, dv3)
        ATTN_STEP(PMASK, ek0, ek1, ev0, ev1, ev2, ev3)
      }
    }
    WG_WAIT(0);
    fence_regs(o); fence_regs(s);
    attn_store(o, (quarter * 4 + wg) * 128 + tile * 64 + warp * 16 + g, head, lane);
    if (tile == 0 && wg == 0) {
      uint32_t kn = 0;
#pragma unroll 2
      for (int i = 0; i < 16; i++) {
        const int key = tid + 128 * i;
        const uint32_t ad = sb + (key >> 6) * 6144 + ((key >> 3) & 7) * 384 + (key & 7) * 16;
        uint32_t w0[4], w1[4], w2[4];
        lds128u(w0, ad); lds128u(w1, ad + 128); lds128u(w2, ad + 256);
        uint32_t n2 = hfma2_bf16(w2[1], w2[1], hmul2_bf16(w2[0], w2[0])), m2 = hmul2_bf16(w0[0], w0[0]);
#pragma unroll
        for (int e = 0; e < 4; e++) { n2 = hfma2_bf16(w1[e], w1[e], n2); if (e) m2 = hfma2_bf16(w0[e], w0[e], m2); }
        const float n = (bf_lo(n2) + bf_hi(n2)) + (bf_lo(m2) + bf_hi(m2));
        kn = max(kn, __float_as_uint(n));
      }
      if ((PMASK >> ((tid >> 3) & 7)) & 1) kn = __float_as_uint(__uint_as_float(kn) * 4.0f);
      kn = __reduce_max_sync(0xffffffffu, kn);
      if (lane == 0) { atomicMax(&s_misc[0], kn); mbar_arrive(bb + 40); }
    }
    if (tile == 0 && (tid & 127) == 32) {
      if (wg == 0) l2_prefetch(reinterpret_cast<const uint8_t*>(ar.wo) + blockIdx.x * 6400, 6400);
      else l2_prefetch(reinterpret_cast<const uint8_t*>(wg == 1 ? ar.wg : wg == 2 ? ar.wu : ar.wd) + blockIdx.x * 15360, 15360);
    }
  }
  {
    mbar_wait(bb + 40, 0);
    const bool bad = !(qn * __uint_as_float(*reinterpret_cast<volatile uint32_t*>(&s_misc[0])) <= 76.0f * 76.0f);
    uint32_t any;
    asm volatile("{\n.reg .pred p, q;\nsetp.ne.u32 p, %1, 0;\nbar.red.or.pred q, %2, 128, p;\nselp.u32 %0, 1, 0, q;\n}\n"
                 : "=r"(any) : "r"((uint32_t)bad), "r"(wg + 9) : "memory");
    if (!any) return;
  }
#pragma unroll 1
  for (int tile = 0; tile < 2; tile++) {
    uint32_t a[6];
    q_load(a, head, tile * 16 + quarter * 4 + wg, warp, lane, qn);
    float o[12], s[32];
    uint32_t p[16];
#pragma unroll
    for (int i = 0; i < 12; i++) o[i] = 0.f;
    float m0 = -INFINITY, m1 = -INFINITY;
#pragma unroll 1
    for (int pass = 0; pass < 2; pass++) {
#pragma unroll 1
      for (int j = 0; j < 32; j++) {
        const uint32_t klo = klo0 + j * 384, vlo = vlo0 + j * 384;
        WG_FENCE();
        wgmma_rs_n64_tb0(s, a[0], a[1], a[2], a[3], mkd(klo, 24), 0);
        wgmma_rs_n64_tb0(s, a[4], a[5], z0, z1, mkd(klo + 16 - (8 << 16), 24), 1);
        WG_COMMIT();
        WG_WAIT(0);
        fence_regs(s);
        if (pass == 0) {
#pragma unroll
          for (int cc = 0; cc < 8; cc++) {
            const float f = ((PMASK >> cc) & 1) ? 2.0f : 1.0f;
            m0 = fmaxf(m0, fmaxf(s[4 * cc], s[4 * cc + 1]) * f);
            m1 = fmaxf(m1, fmaxf(s[4 * cc + 2], s[4 * cc + 3]) * f);
          }
        } else {
#pragma unroll
          for (int cc = 0; cc < 8; cc++) {
            const float f = ((PMASK >> cc) & 1) ? 2.0f : 1.0f;
            p[2 * cc] = pack_bf16(ex2(fmaf(s[4 * cc], f, -m0)), ex2(fmaf(s[4 * cc + 1], f, -m0)));
            p[2 * cc + 1] = pack_bf16(ex2(fmaf(s[4 * cc + 2], f, -m1)), ex2(fmaf(s[4 * cc + 3], f, -m1)));
          }
          fence_regs(p); fence_regs(o);
          WG_FENCE();
#pragma unroll
          for (int kk = 0; kk < 4; kk++) wgmma_rs_n24_tb1(o, p[4 * kk], p[4 * kk + 1], p[4 * kk + 2], p[4 * kk + 3], mkd(vlo + kk * 48, 8), 1);
          WG_COMMIT();
          WG_WAIT(0);
          fence_regs(o);
        }
      }
      if (pass == 0) {
        m0 = fmaxf(m0, __shfl_xor_sync(0xffffffffu, m0, 1)); m0 = fmaxf(m0, __shfl_xor_sync(0xffffffffu, m0, 2));
        m1 = fmaxf(m1, __shfl_xor_sync(0xffffffffu, m1, 1)); m1 = fmaxf(m1, __shfl_xor_sync(0xffffffffu, m1, 2));
      }
    }
    attn_store(o, (quarter * 4 + wg) * 128 + tile * 64 + warp * 16 + g, head, lane);
  }
}

__global__ void __cluster_dims__(2, 1, 1) __launch_bounds__(512, 1)
ka_attn(const __grid_constant__ CUtensorMap tm_x, const __grid_constant__ CUtensorMap tm_w,
        const bf16* __restrict__ x, const bf16* __restrict__ c, const bf16* __restrict__ wqkv, const bf16* __restrict__ wmod,
        const __grid_constant__ AttnArgs ar) {
  extern __shared__ uint8_t smem_raw[];
  __shared__ __align__(8) uint64_t bars[2 * K2_ST + 2 + 8];
  __shared__ __align__(16) float s_red[4][64];
  __shared__ uint32_t s_misc[4];
  const uint32_t sb = (smem_u32(smem_raw) + 1023) & ~1023u;
  const uint32_t lnp = sb + K2_ST * K2_STAGE;
  const uint32_t fb = smem_u32(bars), eb = fb + 8 * K2_ST, p1d = eb + 8 * K2_ST, bb = p1d + 8;
  const int rank = cluster_rank();
  const int wid0 = __shfl_sync(0xffffffffu, threadIdx.x >> 5, 0);
  const int mblk = (blockIdx.x >> 4) * 2 + rank, nblk = (blockIdx.x >> 1) & 7;
  const int m0 = mblk * 128, n0 = nblk * 240;
  const bool mod_cta = blockIdx.x < 100;
  const int mks = blockIdx.x % 5, mcol = (blockIdx.x / 5) * 64;
  PDL_TRIGGER();
  if (blockIdx.x >= 128) {
    const int tid = fresh_tid();
    if (tid == 0) {
      mbar_init(bb, 1); mbar_init(bb + 8, 1);
      asm volatile("fence.mbarrier_init.release.cluster;\n" ::: "memory");
    }
    if (blockIdx.x == 128 && tid < 32) g_flags[tid * 32] = 0u;
    __nanosleep(4000);
    const int part = blockIdx.x - 128 + 2;
    const uint32_t scb = sb + 163840, redb = scb + D_ * 4;
#pragma unroll 1
    for (int i = tid; i < D_; i += 512) sts32(scb + i * 4, __float_as_uint(silu_bf(c[i])));
    __syncthreads();
    const bf16* wp = wmod + part * D_;
    if (tid < 128) {
      if ((tid & 63) == 0) mbar_expect_tx(bb + 8 * (tid >> 6), 81920);
      bulk_g2s(sb + tid * 1280, wp + (size_t)tid * (6 * D_), 1280, bb + 8 * (tid >> 6));
    }
    const int cg = tid % 80, rg = tid / 80;
    float acc[8];
#pragma unroll
    for (int j = 0; j < 8; j++) acc[j] = 0.f;
#pragma unroll 1
    for (int bt = 0; bt < 10; bt++) {
      mbar_wait(bb + 8 * (bt & 1), (bt >> 1) & 1);
      if (rg < 6) {
#pragma unroll 2
        for (int r = rg; r < 64; r += 6) {
          uint32_t w[4];
          lds128u(w, sb + (bt & 1) * 81920 + r * 1280 + cg * 16);
          const float s = __uint_as_float(lds32(scb + (bt * 64 + r) * 4));
          acc[0] += s * bf_lo(w[0]); acc[1] += s * bf_hi(w[0]); acc[2] += s * bf_lo(w[1]); acc[3] += s * bf_hi(w[1]);
          acc[4] += s * bf_lo(w[2]); acc[5] += s * bf_hi(w[2]); acc[6] += s * bf_lo(w[3]); acc[7] += s * bf_hi(w[3]);
        }
      }
      __syncthreads();
      if (bt + 2 < 10 && tid < 64) {
        if (tid == 0) mbar_expect_tx(bb + 8 * (bt & 1), 81920);
        bulk_g2s(sb + (bt & 1) * 81920 + tid * 1280, wp + (size_t)((bt + 2) * 64 + tid) * (6 * D_), 1280, bb + 8 * (bt & 1));
      }
    }
    if (rg < 6) {
#pragma unroll
      for (int j = 0; j < 8; j++) sts32(redb + (rg * D_ + cg * 8 + j) * 4, __float_as_uint(acc[j]));
    }
    __syncthreads();
#pragma unroll 1
    for (int i = tid; i < D_; i += 512) {
      float v = 0.f;
#pragma unroll
      for (int r = 0; r < 6; r++) v += __uint_as_float(lds32(redb + (r * D_ + i) * 4));
      store_mod(part, i, v);
    }
    return;
  }
  if (wid0 >= 8) {
    asm volatile("setmaxnreg.dec.sync.aligned.u32 72;\n");
    const int tid = fresh_tid(), wid = __shfl_sync(0xffffffffu, tid >> 5, 0);
    bf16 cv;
    uint4 wm[8];
    if (wid >= 12 && mod_cta) {
      cv = c[mks * 128 + tid - 384];
#pragma unroll
      for (int i = 0; i < 8; i++)
        wm[i] = __ldg(reinterpret_cast<const uint4*>(wmod + (size_t)(mks * 128 + (wid - 12) * 32 + i * 4 + ((tid & 31) >> 3)) * (6 * D_) + mcol + (tid & 7) * 8));
    }
    if (tid == 256) {
      for (int i = 0; i < K2_ST; i++) { mbar_init(fb + 8 * i, 1); mbar_init(eb + 8 * i, 4); }
      asm volatile("fence.mbarrier_init.release.cluster;\n" ::: "memory");
      tma_prefetch_desc(&tm_x); tma_prefetch_desc(&tm_w);
    }
    if (tid == 288) {
      mbar_init(p1d, 2);
      for (int i = 0; i < 5; i++) mbar_init(bb + 8 * i, 1);
      mbar_init(bb + 40, 4); mbar_init(bb + 48, 1); mbar_init(bb + 56, 1);
      s_misc[0] = 0; s_misc[1] = 0; s_misc[2] = 0;
      asm volatile("fence.mbarrier_init.release.cluster;\n" ::: "memory");
    }
    __syncwarp();
    if (wid == 9) asm volatile("barrier.cluster.arrive.release.aligned;\n" ::: "memory");
    else asm volatile("barrier.cluster.arrive.relaxed.aligned;\n" ::: "memory");
    asm volatile("barrier.cluster.wait.acquire.aligned;\n" ::: "memory");
    if (wid < 11) {
      const int part = wid - 8;
      if ((tid & 31) == 0) {
#pragma unroll 1
        for (int kb = 0; kb < K2_EARLY; kb++) k2_load(sb, fb, &tm_x, &tm_w, kb, m0, n0, rank, part);
        if (part == 0) {
          l2_prefetch(reinterpret_cast<const uint8_t*>(wqkv) + K2_EARLY * 64 * 3840 + blockIdx.x * ((10 - K2_EARLY) * 1920), (10 - K2_EARLY) * 1920);
        }
      }
      __syncwarp();
      named_bar(5, 512);
      if ((tid & 31) == 0) {
#pragma unroll 1
        for (int kb = K2_EARLY; kb < 10; kb++) {
          if (kb >= K2_ST) mbar_wait(eb + 8 * (kb % K2_ST), ((kb / K2_ST) - 1) & 1);
          k2_load(sb, fb, &tm_x, &tm_w, kb, m0, n0, rank, part);
        }
      }
      __syncwarp();
    } else {
      const int pt = tid - 352, mi = pt * 4;
      uint32_t u[10][4], a0 = 1, a1 = 1, need = pt < 128 ? 0x7FFu : 0x3FFu;
      if (wid >= 12 && mod_cta) {
        const int lane = tid & 31;
        const float scv = silu_bf(cv);
        float acc[8];
#pragma unroll
        for (int j = 0; j < 8; j++) acc[j] = 0.f;
#pragma unroll
        for (int i = 0; i < 8; i++) {
          const uint32_t w[4] = {wm[i].x, wm[i].y, wm[i].z, wm[i].w};
          const float sc = __shfl_sync(0xffffffffu, scv, i * 4 + (lane >> 3));
          acc[0] += sc * bf_lo(w[0]); acc[1] += sc * bf_hi(w[0]); acc[2] += sc * bf_lo(w[1]); acc[3] += sc * bf_hi(w[1]);
          acc[4] += sc * bf_lo(w[2]); acc[5] += sc * bf_hi(w[2]); acc[6] += sc * bf_lo(w[3]); acc[7] += sc * bf_hi(w[3]);
        }
#pragma unroll
        for (int o = 8; o < 32; o <<= 1)
#pragma unroll
          for (int j = 0; j < 8; j++) acc[j] += __shfl_xor_sync(0xffffffffu, acc[j], o);
        if (lane < 8) {
          *reinterpret_cast<float4*>(&s_red[wid - 12][lane * 8]) = make_float4(acc[0], acc[1], acc[2], acc[3]);
          *reinterpret_cast<float4*>(&s_red[wid - 12][lane * 8 + 4]) = make_float4(acc[4], acc[5], acc[6], acc[7]);
        }
        named_bar(1, 128);
        if (tid < 448) {
          const int i = tid - 384;
          const float a = (s_red[0][i] + s_red[1][i]) + (s_red[2][i] + s_red[3][i]);
          asm volatile("st.relaxed.gpu.global.b32 [%0], %1;\n" :: "l"(&g_mod1[mks * (2 * D_) + mcol + i]), "r"(nz_bits(a)) : "memory");
        }
      } else {
        __nanosleep(POLL_NS);
      }
#pragma unroll 1
      for (int it = 0;; it++) {
        if (need & 0x400u) asm volatile("ld.relaxed.gpu.global.v2.b32 {%0, %1}, [%2];\n" : "=r"(a0), "=r"(a1) : "l"(&g_stats1[m0 + pt]) : "memory");
#pragma unroll
        for (int i = 0; i < 10; i++)
          if (need & (1u << i))
            asm volatile("ld.relaxed.gpu.global.v4.b32 {%0, %1, %2, %3}, [%4];\n" : "=r"(u[i][0]), "=r"(u[i][1]), "=r"(u[i][2]), "=r"(u[i][3]) : "l"(&g_mod1[i * D_ + mi]) : "memory");
#pragma unroll
        for (int i = 0; i < 10; i++)
          if (min(min(u[i][0], u[i][1]), min(u[i][2], u[i][3])) != 0) need &= ~(1u << i);
        if (min(a0, a1) != 0) need &= ~0x400u;
        if (__all_sync(0xffffffffu, need == 0)) break;
        if (it > (1 << 20)) asm volatile("trap;\n");
      }
      float sa[4], ca[4];
#pragma unroll
      for (int e = 0; e < 4; e++) {
        sa[e] = 0.f; ca[e] = 0.f;
#pragma unroll
        for (int i = 0; i < 5; i++) { sa[e] += __uint_as_float(u[2 * i][e]); ca[e] += __uint_as_float(u[2 * i + 1][e]); }
      }
      const uint32_t c01 = pack_bf16(ca[0], ca[1]), c23 = pack_bf16(ca[2], ca[3]);
      const uint32_t ad = lnp + ln_slot(mi) * 2;
      asm volatile("st.shared.v2.b32 [%0], {%1, %2};\n" :: "r"(ad), "r"(pack_bf16(1.0f + bf_lo(c01), 1.0f + bf_hi(c01))), "r"(pack_bf16(sa[0], sa[1])) : "memory");
      asm volatile("st.shared.v2.b32 [%0], {%1, %2};\n" :: "r"(ad + 16), "r"(pack_bf16(1.0f + bf_lo(c23), 1.0f + bf_hi(c23))), "r"(pack_bf16(sa[2], sa[3])) : "memory");
      if (pt < 128) asm volatile("st.shared.v2.b32 [%0], {%1, %2};\n" :: "r"(lnp + 2560 + pt * 8), "r"(a0), "r"(a1) : "memory");
      named_arrive(5, 512);
    }
    if (wid == 8) {
      mbar_wait(p1d, 0);
      qkv_flags_wait(blockIdx.x >> 2, 0);
      if (tid == 256) mbar_arrive(bb + 48);
      if (tid < 258) kv_load(sb, bb, blockIdx.x >> 2, tid & 1);
      __syncwarp();
    } else if (wid == 12) {
#pragma unroll 1
      for (int q = 0; q < 3; q++) {
        named_bar(2 + q, 160);
        if ((tid & 31) < 4) qkv_store(sb + 2 * K2_STAGE, q * 4 + (tid & 31), nblk, mblk);
        __syncwarp();
      }
      qkv_publish(&g_fq[nblk * 64], tid & 31);
    }
    named_bar(13, 512);
    asm volatile("setmaxnreg.inc.sync.aligned.u32 128;\n");
  } else {
    asm volatile("setmaxnreg.inc.sync.aligned.u32 184;\n");
    {
  const int tid = fresh_tid(), wid = __shfl_sync(0xffffffffu, tid >> 5, 0);
  const int wg = wid >> 2, warp = wid & 3, lane = tid & 31, g = lane >> 2, t = lane & 3;
  {
    const int srow = m0 + nblk * 16 + wid * 2;
    uint2 v[2][5];
#pragma unroll
    for (int r = 0; r < 2; r++)
#pragma unroll
      for (int i = 0; i < 5; i++) v[r][i] = __ldg(reinterpret_cast<const uint2*>(x + (size_t)(srow + r) * D_) + lane + 32 * i);
    asm volatile("barrier.cluster.arrive.relaxed.aligned;\n" ::: "memory");
    float s[2], q[2];
#pragma unroll
    for (int r = 0; r < 2; r++) {
      s[r] = 0.f;
#pragma unroll
      for (int i = 0; i < 5; i++) s[r] += (bf_lo(v[r][i].x) + bf_hi(v[r][i].x)) + (bf_lo(v[r][i].y) + bf_hi(v[r][i].y));
    }
#pragma unroll
    for (int o = 1; o < 32; o <<= 1) { s[0] += __shfl_xor_sync(0xffffffffu, s[0], o); s[1] += __shfl_xor_sync(0xffffffffu, s[1], o); }
#pragma unroll
    for (int r = 0; r < 2; r++) {
      const float mean = s[r] * (1.0f / D_);
      q[r] = 0.f;
#pragma unroll
      for (int i = 0; i < 5; i++) {
        const float a = bf_lo(v[r][i].x) - mean, b = bf_hi(v[r][i].x) - mean, cc = bf_lo(v[r][i].y) - mean, d = bf_hi(v[r][i].y) - mean;
        q[r] += a * a + b * b + cc * cc + d * d;
      }
    }
#pragma unroll
    for (int o = 1; o < 32; o <<= 1) { q[0] += __shfl_xor_sync(0xffffffffu, q[0], o); q[1] += __shfl_xor_sync(0xffffffffu, q[1], o); }
    if (lane < 2) {
      const float rstd = rsqrtf((lane ? q[1] : q[0]) * (1.0f / D_) + LN_EPS), nm = -(lane ? s[1] : s[0]) * (1.0f / D_) * rstd;
      asm volatile("st.relaxed.gpu.global.v2.b32 [%0], {%1, %2};\n" :: "l"(&g_stats1[srow + lane]), "r"(nz_bits(rstd)), "r"(nz_bits(nm)) : "memory");
    }
    asm volatile("barrier.cluster.wait.acquire.aligned;\n" ::: "memory");
  }
  const int row0 = m0 + wg * 64 + warp * 16 + g;
  named_bar(5, 512);
  float2 st0, st1;
  asm volatile("ld.shared.v2.f32 {%0, %1}, [%2];\n" : "=f"(st0.x), "=f"(st0.y) : "r"(lnp + 2560 + (row0 - m0) * 8) : "memory");
  asm volatile("ld.shared.v2.f32 {%0, %1}, [%2];\n" : "=f"(st1.x), "=f"(st1.y) : "r"(lnp + 2560 + (row0 - m0 + 8) * 8) : "memory");
  const int lrow = wg * 64 + warp * 16 + (lane & 7) + ((lane >> 3) & 1) * 8;
  const uint32_t a_off = lrow * 128, a_x = lane & 7, a_c = lane >> 4;
  float acc[64], acd[56];
  uint32_t af[4][4], raw[4], prm[4];
  mbar_wait(fb, 0);
  ldsm_x4(raw, sb + a_off + ((a_c ^ a_x) << 4));
  lds128u(prm, lnp + t * 16);
  ln_frag(af[0], raw, prm, st0, st1);
  ldsm_x4(raw, sb + a_off + (((2 + a_c) ^ a_x) << 4));
  lds128u(prm, lnp + (4 + t) * 16);
#pragma unroll P1_UNROLL
  for (int kb = 0; kb < 10; kb++) {
    const int s = kb % K2_ST, s1 = (kb + 1) % K2_ST;
    const uint32_t a = sb + s * K2_STAGE, blo = desc_lo(a + 16384, 8192);
    if (kb == 10 - K2_LEAD && wg == 1) {
      WG_WAIT(0);
      named_arrive(7, 256);
      named_bar(6, 256);
    }
#pragma unroll
    for (int kk = 0; kk < 4; kk++) {
      fence_regs(af[kk]);
      WG_FENCE();
      wgmma_rs_n128_tb1(acc, af[kk][0], af[kk][1], af[kk][2], af[kk][3], mkd(blo + kk * 128, DESC_HI_SW128), (kb | kk) != 0);
      wgmma_rs_n112_tb1(acd, af[kk][0], af[kk][1], af[kk][2], af[kk][3], mkd(blo + 1024 + kk * 128, DESC_HI_SW128), (kb | kk) != 0);
      WG_COMMIT();
      if (kk == 3 && kb == 9 && wg == 0) named_arrive(6, 256);
      ln_frag(af[(kk + 1) & 3], raw, prm, st0, st1);
      WG_WAIT(P1W);
      if (kk == P1W - 1 && kb >= 1 && kb - 1 + K2_ST < 10 && (tid & 127) < 2) mbar_arrive_cluster(eb + 8 * ((kb - 1) % K2_ST), tid & 1);
      if (kk == 2 && kb < 9) mbar_wait(fb + 8 * s1, ((kb + 1) / K2_ST) & 1);
      ldsm_x4(raw, (kk < 2 ? a : sb + s1 * K2_STAGE) + a_off + (((((kk + 2) & 3) * 2 + a_c) ^ a_x) << 4));
      lds128u(prm, lnp + (kb * 16 + (kk + 2) * 4 + t) * 16);
    }
  }
  WG_WAIT(0);
  fence_regs(acc); fence_regs(acd);
  if ((tid & 127) == 0) mbar_arrive(p1d);
  if (wg == 0) { named_arrive(8, 256); named_bar(7, 256); } else named_bar(8, 256);
  static_assert(K2_LEAD <= 3, "staging sits in stages 2 and 3 (second half of the K/V area)");
  const uint32_t stg = sb + (2 + wg) * K2_STAGE;
  const bool p0 = (PMASK >> ((row0 >> 3) & 7)) & 1, p1 = (PMASK >> (((row0 >> 3) + 1) & 7)) & 1;
  const uint32_t base = stg + warp * 768 + g * 16;
  {
    uint32_t off[5];
#pragma unroll
    for (int i = 0; i < 5; i++) {
      const int cr = 8 * i + 2 * t, hr = cr >= 20, d = cr - 20 * hr;
      off[i] = base + hr * 3072 + (d >> 3) * 128 + (d & 7) * 2;
    }
#pragma unroll
    for (int q = 0; q < 3; q++) {
      const int which = (nblk * 12 + q * 4) >> 5;
      const float f0 = which == 0 ? QSCALE : (which == 1 && p0) ? 0.5f : 1.0f;
      const float f1 = which == 0 ? QSCALE : (which == 1 && p1) ? 0.5f : 1.0f;
#pragma unroll
      for (int jj = 0; jj < 10; jj++) {
        const int j = q * 10 + jj;
        const uint32_t dst = off[j % 5] + (j / 5) * 6144;
        const float* v = j < 16 ? &acc[4 * j] : &acd[4 * (j - 16)];
        sts32(dst, pack_bf16(v[0] * f0, v[1] * f0));
        sts32(dst + 384, pack_bf16(v[2] * f1, v[3] * f1));
      }
      const uint32_t dst = base + (t + 4 * q) * 3072 + 256 + 8;
      const uint32_t lo0 = which == 2 ? 0x00003F80u : (p0 ? KPAD_LO : 0u), hi0 = (which == 1 && p0) ? KPAD_HI : 0u;
      const uint32_t lo1 = which == 2 ? 0x00003F80u : (p1 ? KPAD_LO : 0u), hi1 = (which == 1 && p1) ? KPAD_HI : 0u;
      asm volatile("st.shared.v2.b32 [%0], {%1, %2};\n" :: "r"(dst), "r"(lo0), "r"(hi0) : "memory");
      asm volatile("st.shared.v2.b32 [%0], {%1, %2};\n" :: "r"(dst + 384), "r"(lo1), "r"(hi1) : "memory");
      asm volatile("fence.proxy.async.shared::cta;\n" ::: "memory");
      if (wg == 0) named_arrive(2 + q, 160);
    }
  }
    }
    asm volatile("setmaxnreg.dec.sync.aligned.u32 128;\n");
    named_arrive(13, 512);
  }
  attn_phase(sb, bb, s_misc, ar);
}

struct KMaps { CUtensorMap o, wo, wo16, x, x16, x2, x2_16, x2_128, wg, wu, hh, hh128, wd, out; };
constexpr int KW_ST = 6, KG_ST = 3, KD_ST = 5;
constexpr int KW_B16 = 81920, KW_A = KW_B16 + 20480, KW_RES = KW_A + KW_ST * 16384, KW_RES16 = KW_RES + 16384;
constexpr int KG_STAGE = 65536, KM_LNP = KW_RES16 + 4096, KD_RES = 65536;
constexpr int KM_STAT = KM_LNP + 2560, KM_SMEM = KM_STAT + 1024 + 1024;
#define KW_WIN 1
#define DHOLD 3
#define KG_PRE 1
#define KG_LEAD 1
#define KD_LEAD 2
__device__ __forceinline__ uint32_t kd_off(int s) { return s * 32768 + (s >= 2 ? 49152 : 0); }
__device__ __forceinline__ float2 merge_stats(int row) {
  float2 p[8];
#pragma unroll
  for (int i = 0; i < 8; i++) p[i] = __ldcg(&g_stats2[i * S_ + row]);
  float mean = 0.f;
#pragma unroll
  for (int i = 0; i < 8; i++) mean += p[i].x;
  mean *= 0.125f;
  float q = 0.f;
#pragma unroll
  for (int i = 0; i < 8; i++) { const float d = p[i].x - mean; q += p[i].y + 80.0f * d * d; }
  const float rstd = rsqrtf(q * (1.0f / D_) + LN_EPS);
  return make_float2(rstd, -mean * rstd);
}
__device__ __forceinline__ void flag_signal(unsigned int* f) {
  asm volatile("cp.async.bulk.wait_group 0;\n" ::: "memory");
  asm volatile("fence.proxy.async.global;\n" ::: "memory");
  asm volatile("red.release.gpu.global.add.u32 [%0], 1;\n" :: "l"(f) : "memory");
}

__global__ void __cluster_dims__(2, 1, 1) __launch_bounds__(384, 1)
km_mlp(const __grid_constant__ KMaps tm) {
  extern __shared__ uint8_t smem_raw[];
  __shared__ __align__(8) uint64_t bars[40];
  const uint32_t sb = (smem_u32(smem_raw) + 1023) & ~1023u;
  const uint32_t fbW = smem_u32(bars), ebW = fbW + 48, wb = ebW + 32, rbW = wb + 40, fbG = rbW + 8, ebG = fbG + 24, fbD = ebG + 24, ebD = fbD + 40,
                 rbD = ebD + 40, pdW = rbD + 8, pdG = pdW + 8, gst = pdG + 8, depG = gst + 8;
  const int tid = threadIdx.x, rank = cluster_rank();
  const int wid = __shfl_sync(0xffffffffu, tid >> 5, 0);
  const int mW = blockIdx.x >> 3, nW = blockIdx.x & 7;
  const int mG = (blockIdx.x >> 4) * 2 + rank, nG = (blockIdx.x >> 1) & 7;
  const bool do_d = nG < 5;
  if (tid == 256) {
    tma_prefetch_desc(&tm.o);
    for (int i = 0; i < KW_ST; i++) mbar_init(fbW + 8 * i, 1);
    for (int i = 0; i < 4; i++) mbar_init(ebW + 8 * i, 16);
    for (int i = 0; i < KG_ST; i++) { mbar_init(fbG + 8 * i, 1); mbar_init(ebG + 8 * i, 4); }
    for (int i = 0; i < KD_ST; i++) { mbar_init(fbD + 8 * i, 1); mbar_init(ebD + 8 * i, 4); }
    mbar_init(rbD, 1); mbar_init(pdW, 4); mbar_init(pdG, 4); mbar_init(gst, 2); mbar_init(depG, 1);
    asm volatile("fence.mbarrier_init.release.cluster;\n" ::: "memory");
  }
  if (tid == 288) {
    tma_prefetch_desc(&tm.wo); tma_prefetch_desc(&tm.wo16);
    for (int i = 0; i < 6; i++) mbar_init(wb + 8 * i, 1);
    asm volatile("fence.mbarrier_init.release.cluster;\n" ::: "memory");
  }
  __syncwarp();
  cluster_sync();
  if (wid >= 8) {
    asm volatile("setmaxnreg.dec.sync.aligned.u32 24;\n");
    if (tid == 288) {
#pragma unroll 1
      for (int i = 0; i < 5; i++) {
        if (i >= KW_WIN) mbar_wait(wb + 8 * (i - KW_WIN), 0);
        mbar_expect_tx(wb + 8 * i, 20480);
        tma_load(sb + i * 16384, &tm.wo, nW * 64, i * 128, wb + 8 * i);
        tma_load(sb + i * 16384 + 8192, &tm.wo, nW * 64, i * 128 + 64, wb + 8 * i);
        tma_load(sb + KW_B16 + i * 4096, &tm.wo16, 512 + nW * 16, i * 128, wb + 8 * i);
      }
      mbar_wait(wb + 8 * (5 - KW_WIN), 0);
      mbar_expect_tx(rbW, 20480);
      for (int i = 0; i < 2; i++) {
        tma_load(sb + KW_RES + i * 8192, &tm.x, nW * 64, mW * 128 + i * 64, rbW);
        tma_load(sb + KW_RES16 + i * 2048, &tm.x16, 512 + nW * 16, mW * 128 + i * 64, rbW);
      }
      tma_prefetch_desc(&tm.x2); tma_prefetch_desc(&tm.x2_16); tma_prefetch_desc(&tm.x2_128); tma_prefetch_desc(&tm.wg); tma_prefetch_desc(&tm.wu);
      tma_prefetch_desc(&tm.hh); tma_prefetch_desc(&tm.hh128); tma_prefetch_desc(&tm.wd); tma_prefetch_desc(&tm.out);
      {
        const CUtensorMap* tw = rank == 0 ? &tm.wg : &tm.wu;
        mbar_wait(pdW, 0);
#pragma unroll 1
        for (int kb = 0; kb < 10; kb++) {
          const int s = kb % KG_ST;
          if (kb == KG_PRE) mbar_wait(depG, 0);
          if (kb >= KG_ST) mbar_wait(ebG + 8 * s, ((kb / KG_ST) - 1) & 1);
          mbar_expect_tx(fbG + 8 * s, KG_STAGE);
          for (int i = 0; i < 3; i++) tma_load_mc(sb + s * KG_STAGE + 16384 + (rank * 3 + i) * 8192, tw, nG * 192 + i * 64, kb * 64, fbG + 8 * s);
        }
      }
      if (do_d) {
        mbar_wait(pdG, 0);
#pragma unroll 1
        for (int i = 0; i < 24; i++) {
          const int s = i % KD_ST, kc = i < 3 ? nG * 3 + i : (i - 3 < nG * 3 ? i - 3 : i);
          if (i == DHOLD) mbar_wait(gst, 0);
          if (i >= KD_ST) mbar_wait(ebD + 8 * s, ((i / KD_ST) - 1) & 1);
          mbar_expect_tx(fbD + 8 * s, i < 3 ? 16384 : 32768);
          tma_load_mc(sb + kd_off(s) + 16384 + rank * 8192, &tm.wd, nG * 128 + rank * 64, kc * 64, fbD + 8 * s);
        }
      }
    }
    if (wid >= 10) {
      const int wg = wid - 10;
      PDL_WAIT();
      {
        const int l = tid & 31;
        uint2* z = wg ? reinterpret_cast<uint2*>(g_mod1) + blockIdx.x * 25 : g_stats1 + blockIdx.x * 16;
        if (l < (wg ? 25 : 16)) z[l] = make_uint2(0u, 0u);
        if (blockIdx.x == 0 && l < 16) g_fq[l * 32] = 0u;
      }
      __syncwarp();
      named_bar(2 + wg, 160);
      if ((tid & 31) == 0) {
        tma_store(&tm.x2, nW * 64, mW * 128 + wg * 64, sb + KW_RES + wg * 8192);
        tma_store(&tm.x2_16, 512 + nW * 16, mW * 128 + wg * 64, sb + KW_RES16 + wg * 2048);
        asm volatile("cp.async.bulk.global.shared::cta.bulk_group [%0], [%1], %2;\n" :: "l"(&g_stats2[nW * S_ + mW * 128 + wg * 64]), "r"(sb + KM_STAT + wg * 512), "r"(512) : "memory");
        asm volatile("cp.async.bulk.commit_group;\n" ::: "memory");
        flag_signal(&g_flags[mW * 32]);
      }
      __syncwarp();
#pragma unroll 1
      for (int i = 0; i < 3; i++) {
        named_bar(8 + wg * 3 + i, 160);
        if ((tid & 31) == 0) tma_store(&tm.hh, nG * 192 + i * 64, mG * 128 + wg * 64, sb + KG_STAGE + wg * 24576 + i * 8192);
        __syncwarp();
      }
      if ((tid & 31) == 0) {
        asm volatile("cp.async.bulk.commit_group;\n" ::: "memory");
        flag_signal(&g_flags[(16 + mG) * 32]);
        mbar_arrive(gst);
      }
    }
    if (tid == 256) {
      PDL_WAIT();
#pragma unroll 1
      for (int kb = 0; kb < 10; kb++) {
        const int s = kb % KW_ST;
        if (kb >= KW_ST) mbar_wait(ebW + 8 * s, 0);
        mbar_expect_tx(fbW + 8 * s, 16384);
        tma_load_mc(sb + KW_A + s * 16384 + rank * 8192, &tm.o, kb * 64, mW * 128 + rank * 64, fbW + 8 * s);
      }
      mbar_wait(pdW, 0);
      flag_wait(&g_flags[mG * 32], 16);
      mbar_arrive(depG);
#pragma unroll 1
      for (int kb = 0; kb < 10; kb++) {
        const int s = kb % KG_ST;
        if (kb >= KG_ST) mbar_wait(ebG + 8 * s, ((kb / KG_ST) - 1) & 1);
        tma_load(sb + s * KG_STAGE, &tm.x2_128, kb * 64, mG * 128, fbG + 8 * s);
      }
      if (do_d) {
        mbar_wait(pdG, 0);
        flag_wait(&g_flags[(16 + mG) * 32], 16);
#pragma unroll 1
        for (int i = 3; i < 24; i++) {
          const int s = i % KD_ST, kc = i - 3 < nG * 3 ? i - 3 : i;
          if (i >= KD_ST) mbar_wait(ebD + 8 * s, ((i / KD_ST) - 1) & 1);
          tma_load(sb + kd_off(s), &tm.hh128, kc * 64, mG * 128, fbD + 8 * s);
          if (i == KD_ST + 2) {
            mbar_wait(gst, 0);
            mbar_expect_tx(rbD, 32768);
            for (int q = 0; q < 4; q++) tma_load(sb + KD_RES + q * 8192, &tm.x2, nG * 128 + (q & 1) * 64, mG * 128 + (q >> 1) * 64, rbD);
          }
        }
      }
    }
  } else {
    asm volatile("setmaxnreg.inc.sync.aligned.u32 240;\n");
    const int wg = wid >> 2, warp = wid & 3, lane = tid & 31, g = lane >> 2, t = lane & 3;
    const int r0 = warp * 16 + g;
    const uint32_t a_row = (wg * 64 + warp * 16 + (lane & 7) + ((lane >> 3) & 1) * 8) * 128, a_x = lane & 7, a_c = lane >> 4;
    {
      float acc[32], acd[8];
#pragma unroll
      for (int i = 0; i < 32; i++) acc[i] = 0.f;
#pragma unroll
      for (int i = 0; i < 8; i++) acd[i] = 0.f;
      fence_regs(acc); fence_regs(acd);
      constexpr uint32_t HI32 = (256 >> 4) | (3u << 30);
      uint32_t af[2][4][4];
#pragma unroll 1
      for (int k2 = 0; k2 < 10; k2 += 2) {
        mbar_wait(wb + 4 * k2, 0);
#pragma unroll
        for (int h = 0; h < 2; h++) {
          const int kb = k2 + h, s = kb >= KW_ST ? kb - KW_ST : kb;
          const uint32_t blo = desc_lo(sb + kb * 8192, 8192), clo = desc_lo(sb + KW_B16 + kb * 2048, 16);
          mbar_wait(fbW + 8 * s, kb >= KW_ST);
#pragma unroll
          for (int kk = 0; kk < 4; kk++) ldsm_x4(af[h][kk], sb + KW_A + a_row + s * 16384 + (((kk * 2 + a_c) ^ a_x) << 4));
#pragma unroll
          for (int kk = 0; kk < 4; kk++) fence_regs(af[h][kk]);
          WG_FENCE();
#pragma unroll
          for (int kk = 0; kk < 4; kk++) wgmma_rs_n64_tb1(acc, af[h][kk][0], af[h][kk][1], af[h][kk][2], af[h][kk][3], mkd(blo + kk * 128, DESC_HI_SW128), 1);
#pragma unroll
          for (int kk = 0; kk < 4; kk++) wgmma_rs_n16_tb1(acd, af[h][kk][0], af[h][kk][1], af[h][kk][2], af[h][kk][3], mkd(clo + kk * 32, HI32), 1);
          WG_COMMIT();
          if (kb + KW_ST < 10 && lane < 2) mbar_arrive_cluster(ebW + 8 * kb, lane);
          WG_WAIT(1);
        }
      }
      PDL_WAIT();
      float2 gv[10];
#pragma unroll
      for (int j = 0; j < 10; j++) gv[j] = *reinterpret_cast<const float2*>(g_ga + (j < 8 ? nW * 64 + 8 * j : 512 + nW * 16 + 8 * (j - 8)) + 2 * t);
      if (tid < D_ / 4) {
        const uint4 v = g_ln2[tid];
        asm volatile("st.shared.v4.b32 [%0], {%1, %2, %3, %4};\n" :: "r"(sb + KM_LNP + tid * 16), "r"(v.x), "r"(v.y), "r"(v.z), "r"(v.w) : "memory");
      }
      WG_WAIT(0);
      fence_regs(acc); fence_regs(acd);
      if ((tid & 127) < 2) mbar_arrive_cluster(pdW, tid & 1);
      mbar_wait(rbW, 0);
      float y[40];
#pragma unroll
      for (int j = 0; j < 10; j++) {
        const uint32_t ad = j < 8 ? sb + KW_RES + wg * 8192 + r0 * 128 + t * 4 + ((j ^ g) << 4) : sb + KW_RES16 + wg * 2048 + r0 * 32 + (j - 8) * 16 + t * 4;
        const uint32_t o8 = j < 8 ? 1024 : 256;
        const float* a = j < 8 ? &acc[4 * j] : &acd[4 * (j - 8)];
        const uint32_t x0 = lds32(ad), x1 = lds32(ad + o8);
        const uint32_t y0 = pack_bf16(fmaf(gv[j].x, a[0], bf_lo(x0)), fmaf(gv[j].y, a[1], bf_hi(x0)));
        const uint32_t y1 = pack_bf16(fmaf(gv[j].x, a[2], bf_lo(x1)), fmaf(gv[j].y, a[3], bf_hi(x1)));
        sts32(ad, y0); sts32(ad + o8, y1);
        y[4 * j] = bf_lo(y0); y[4 * j + 1] = bf_hi(y0); y[4 * j + 2] = bf_lo(y1); y[4 * j + 3] = bf_hi(y1);
      }
      float s0 = 0.f, s1 = 0.f;
#pragma unroll
      for (int j = 0; j < 10; j++) { s0 += y[4 * j] + y[4 * j + 1]; s1 += y[4 * j + 2] + y[4 * j + 3]; }
      s0 += __shfl_xor_sync(0xffffffffu, s0, 1); s0 += __shfl_xor_sync(0xffffffffu, s0, 2);
      s1 += __shfl_xor_sync(0xffffffffu, s1, 1); s1 += __shfl_xor_sync(0xffffffffu, s1, 2);
      s0 *= (1.0f / 80); s1 *= (1.0f / 80);
      float q0 = 0.f, q1 = 0.f;
#pragma unroll
      for (int j = 0; j < 10; j++) {
        const float a = y[4 * j] - s0, b = y[4 * j + 1] - s0, cc = y[4 * j + 2] - s1, d = y[4 * j + 3] - s1;
        q0 += a * a + b * b; q1 += cc * cc + d * d;
      }
      q0 += __shfl_xor_sync(0xffffffffu, q0, 1); q0 += __shfl_xor_sync(0xffffffffu, q0, 2);
      q1 += __shfl_xor_sync(0xffffffffu, q1, 1); q1 += __shfl_xor_sync(0xffffffffu, q1, 2);
      const uint32_t sst = sb + KM_STAT + wg * 512;
      if (t < 2) asm volatile("st.shared.v2.f32 [%0], {%1, %2};\n" :: "r"(sst + (r0 + t * 8) * 8), "f"(t ? s1 : s0), "f"(t ? q1 : q0) : "memory");
      asm volatile("fence.proxy.async.shared::cta;\n" ::: "memory");
      named_arrive(2 + wg, 160);
    }
    {
      named_bar(1, 256);
      mbar_wait(depG, 0);
      const int row0 = mG * 128 + wg * 64 + r0;
      const float2 st0 = merge_stats(row0), st1 = merge_stats(row0 + 8);
      const uint32_t lnp = sb + KM_LNP;
      float ag[96], au[96];
      uint32_t af[2][4], raw[4], prm[4];
      mbar_wait(fbG, 0);
      ldsm_x4(raw, sb + a_row + ((a_c ^ a_x) << 4));
      lds128u(prm, lnp + t * 16);
      ln_frag(af[0], raw, prm, st0, st1);
#pragma unroll 1
      for (int kb = 0; kb < 10; kb++) {
        const int s = kb % KG_ST;
        const uint32_t a = sb + s * KG_STAGE, blo = desc_lo(a + 16384, 8192);
        if (kb == 10 - KG_LEAD && wg == 1) {
          WG_WAIT(0);
          named_arrive(7, 256);
          named_bar(6, 256);
        }
#pragma unroll
        for (int kk = 0; kk < 4; kk++) {
          if (kk < 3) {
            ldsm_x4(raw, a + a_row + ((((kk + 1) * 2 + a_c) ^ a_x) << 4));
            lds128u(prm, lnp + (kb * 16 + (kk + 1) * 4 + t) * 16);
          } else if (kb < 9) {
            const int s1 = (kb + 1) % KG_ST;
            mbar_wait(fbG + 8 * s1, ((kb + 1) / KG_ST) & 1);
            ldsm_x4(raw, sb + s1 * KG_STAGE + a_row + ((a_c ^ a_x) << 4));
            lds128u(prm, lnp + (kb * 16 + 16 + t) * 16);
          }
          fence_regs(af[kk & 1]);
          WG_FENCE();
          wgmma_rs_n192_tb1(ag, af[kk & 1][0], af[kk & 1][1], af[kk & 1][2], af[kk & 1][3], mkd(blo + kk * 128, DESC_HI_SW128), (kb | kk) != 0);
          wgmma_rs_n192_tb1(au, af[kk & 1][0], af[kk & 1][1], af[kk & 1][2], af[kk & 1][3], mkd(blo + 1536 + kk * 128, DESC_HI_SW128), (kb | kk) != 0);
          WG_COMMIT();
          if (kk == 3 && kb == 9 && wg == 0) named_arrive(6, 256);
          WG_WAIT(1);
          if (kk == 0 && kb >= 1 && kb - 1 + KG_ST < 10 && (tid & 127) < 2) mbar_arrive_cluster(ebG + 8 * ((kb - 1) % KG_ST), tid & 1);
          ln_frag(af[(kk + 1) & 1], raw, prm, st0, st1);
        }
      }
      WG_WAIT(0);
      fence_regs(ag); fence_regs(au);
      if (do_d && (tid & 127) < 2) mbar_arrive_cluster(pdG, tid & 1);
      if (wg == 0) named_bar(7, 256);
      static_assert(KG_LEAD == 1 || KG_LEAD == 2, "hh staging sits in stage 1");
      const uint32_t stg = sb + KG_STAGE + wg * 24576;
      const uint32_t ob = stg + r0 * 128 + t * 4;
#pragma unroll
      for (int j = 0; j < 24; j++) {
        const uint32_t ad = ob + (j >> 3) * 8192 + (((j & 7) ^ g) << 4);
        const uint32_t g0 = pack_bf16(ag[4 * j], ag[4 * j + 1]), g1 = pack_bf16(ag[4 * j + 2], ag[4 * j + 3]);
        const uint32_t u0 = pack_bf16(au[4 * j], au[4 * j + 1]), u1 = pack_bf16(au[4 * j + 2], au[4 * j + 3]);
        sts32(ad, hmul2_bf16(g0, u0));
        sts32(ad + 1024, hmul2_bf16(g1, u1));
        if ((j & 7) == 7) {
          asm volatile("fence.proxy.async.shared::cta;\n" ::: "memory");
          if (j < 23) named_arrive(8 + wg * 3 + (j >> 3), 160); else named_bar(8 + wg * 3 + 2, 160);
        }
      }
    }
    if (do_d) {
      float acc[64];
      float2 gv[16];
#pragma unroll
      for (int j = 0; j < 16; j++) gv[j] = *reinterpret_cast<const float2*>(g_gb + nG * 128 + 8 * j + 2 * t);
      __syncwarp();
#pragma unroll 1
      for (int kb = 0; kb < 24; kb++) {
        const int s = kb % KD_ST;
        const uint32_t a = sb + kd_off(s);
        const uint32_t alo = desc_lo(kb < 3 ? sb + KG_STAGE + wg * 24576 + kb * 8192 : a + wg * 8192, 16), blo = desc_lo(a + 16384, 8192);
        if (kb == 24 - KD_LEAD && wg == 1) named_bar(6, 256);
        mbar_wait(fbD + 8 * s, (kb / KD_ST) & 1);
        WG_FENCE();
#pragma unroll
        for (int kk = 0; kk < 4; kk++) wgmma_ss_n128_tb1(acc, mkd(alo + kk * 2, DESC_HI_SW128), mkd(blo + kk * 128, DESC_HI_SW128), (kb | kk) != 0);
        WG_COMMIT();
        if (kb == 23 && wg == 0) named_arrive(6, 256);
        WG_WAIT(1);
        if (kb >= 1 && kb - 1 + KD_ST < 24 && (tid & 127) < 2) mbar_arrive_cluster(ebD + 8 * ((kb - 1) % KD_ST), tid & 1);
      }
      WG_WAIT(0);
      fence_regs(acc);
      mbar_wait(rbD, 0);
      const uint32_t rbase = sb + KD_RES + wg * 16384 + r0 * 128 + t * 4;
#pragma unroll
      for (int j = 0; j < 16; j++) {
        const uint32_t ad = rbase + (j >> 3) * 8192 + (((j & 7) ^ g) << 4);
        const uint32_t x0 = lds32(ad), x1 = lds32(ad + 1024);
        sts32(ad, pack_bf16(fmaf(gv[j].x, acc[4 * j], bf_lo(x0)), fmaf(gv[j].y, acc[4 * j + 1], bf_hi(x0))));
        sts32(ad + 1024, pack_bf16(fmaf(gv[j].x, acc[4 * j + 2], bf_lo(x1)), fmaf(gv[j].y, acc[4 * j + 3], bf_hi(x1))));
      }
      asm volatile("fence.proxy.async.shared::cta;\n" ::: "memory");
      named_bar(4 + wg, 128);
      if ((tid & 127) == 0) {
        tma_store(&tm.out, nG * 128, mG * 128 + wg * 64, sb + KD_RES + wg * 16384);
        tma_store(&tm.out, nG * 128 + 64, mG * 128 + wg * 64, sb + KD_RES + wg * 16384 + 8192);
        asm volatile("cp.async.bulk.commit_group;\n" ::: "memory");
        asm volatile("cp.async.bulk.wait_group.read 0;\n" ::: "memory");
      }
    }
  }
}

typedef CUresult (*EncodeFn)(CUtensorMap*, CUtensorMapDataType, cuuint32_t, void*, const cuuint64_t*, const cuuint64_t*, const cuuint32_t*,
                             const cuuint32_t*, CUtensorMapInterleave, CUtensorMapSwizzle, CUtensorMapL2promotion, CUtensorMapFloatOOBfill);
static CUtensorMap make_map(EncodeFn fn, const void* ptr, int inner, int outer, int b0 = 64, int b1 = 64,
                            CUtensorMapSwizzle sw = CU_TENSOR_MAP_SWIZZLE_128B) {
  CUtensorMap m;
  cuuint64_t dims[2] = {(cuuint64_t)inner, (cuuint64_t)outer};
  cuuint64_t strides[1] = {(cuuint64_t)inner * 2};
  cuuint32_t box[2] = {(cuuint32_t)b0, (cuuint32_t)b1}, es[2] = {1, 1};
  fn(&m, CU_TENSOR_MAP_DATA_TYPE_BFLOAT16, 2, const_cast<void*>(ptr), dims, strides, box, es, CU_TENSOR_MAP_INTERLEAVE_NONE,
     sw, sw == CU_TENSOR_MAP_SWIZZLE_128B ? CU_TENSOR_MAP_L2_PROMOTION_L2_256B : CU_TENSOR_MAP_L2_PROMOTION_L2_128B, CU_TENSOR_MAP_FLOAT_OOB_FILL_NONE);
  return m;
}
template <typename... KArgs, typename... Args>
static void launch(void (*kern)(KArgs...), int grid, int block, int smem, bool pdl, Args... args) {
  cudaLaunchConfig_t cfg = {};
  cfg.gridDim = dim3(grid); cfg.blockDim = dim3(block); cfg.dynamicSmemBytes = smem; cfg.stream = cudaStreamPerThread;
  cudaLaunchAttribute at[1];
  at[0].id = cudaLaunchAttributeProgrammaticStreamSerialization;
  at[0].val.programmaticStreamSerializationAllowed = 1;
  cfg.attrs = at; cfg.numAttrs = pdl ? 1 : 0;
  cudaLaunchKernelEx(&cfg, kern, KArgs(args)...);
}

extern "C" void kernel_launch(void* const* d_in, const int* in_sizes, int n_in, void* d_out, int out_size) {
  const bf16* x = (const bf16*)d_in[0];
  const bf16* wqkv = (const bf16*)d_in[1];
  const bf16* wo = (const bf16*)d_in[2];
  const bf16* wg = (const bf16*)d_in[4];
  const bf16* wu = (const bf16*)d_in[5];
  const bf16* wd = (const bf16*)d_in[6];
  const bf16* c = (const bf16*)d_in[7];
  const bf16* wmod = (const bf16*)d_in[8];
  void* fnp = nullptr;
  cudaDriverEntryPointQueryResult qr;
  cudaGetDriverEntryPoint("cuTensorMapEncodeTiled", &fnp, cudaEnableDefault, &qr);
  EncodeFn fn = (EncodeFn)fnp;
  void *po, *px2, *phh;
  cudaGetSymbolAddress(&po, g_o); cudaGetSymbolAddress(&px2, g_x2); cudaGetSymbolAddress(&phh, g_hh);
  CUtensorMap tm_x = make_map(fn, x, D_, S_), tm_wqkv = make_map(fn, wqkv, 3 * D_, D_);
  KMaps km;
  km.o = make_map(fn, po, D_, S_); km.wo = make_map(fn, wo, D_, D_); km.wo16 = make_map(fn, wo, D_, D_, 16, 128, CU_TENSOR_MAP_SWIZZLE_32B);
  km.x = tm_x; km.x16 = make_map(fn, x, D_, S_, 16, 64, CU_TENSOR_MAP_SWIZZLE_NONE);
  km.x2 = make_map(fn, px2, D_, S_); km.x2_128 = make_map(fn, px2, D_, S_, 64, 128); km.x2_16 = make_map(fn, px2, D_, S_, 16, 64, CU_TENSOR_MAP_SWIZZLE_NONE);
  km.wg = make_map(fn, wg, F_, D_); km.wu = make_map(fn, wu, F_, D_); km.hh = make_map(fn, phh, F_, S_); km.hh128 = make_map(fn, phh, F_, S_, 64, 128);
  km.wd = make_map(fn, wd, D_, F_); km.out = make_map(fn, d_out, D_, S_);
  cudaFuncSetAttribute(ka_attn, cudaFuncAttributeMaxDynamicSharedMemorySize, KA_SMEM);
  cudaFuncSetAttribute(km_mlp, cudaFuncAttributeMaxDynamicSharedMemorySize, KM_SMEM);
  AttnArgs ar = {wo, wg, wu, wd};
  launch(ka_attn, 132, 512, KA_SMEM, false, make_map(fn, x, D_, S_, 64, 128), tm_wqkv, x, c, wqkv, wmod, ar);
  launch(km_mlp, 128, 384, KM_SMEM, true, km);
}
```
